```python
import torch

def _softmax(x, axis=-1):
    return torch.softmax(x, dim=axis)
def _gelu(x):
    return torch.nn.functional.gelu(x, approximate="tanh")
def _silu(x):
    return torch.nn.functional.silu(x)
def _sigmoid(x):
    return torch.sigmoid(x)
def _layernorm(x, axis=-1, eps=1e-5):
    m = x.mean(dim=axis, keepdim=True)
    v = x.var(dim=axis, keepdim=True, unbiased=False)
    return (x - m) / torch.sqrt(v + eps)
def _scatter_add(tgt, idx, src, axis=0):
    return tgt.clone().index_add_(axis, idx, src)
def _segment_sum(src, seg, n):
    out = torch.zeros((n,) + src.shape[1:], dtype=src.dtype)
    return out.index_add_(0, seg, src)
def _pad(x, pw):
    flat = tuple(v for pair in reversed(pw) for v in pair)
    return torch.nn.functional.pad(x, flat)

kernel_name = 'sequential_preLN__linear_kernel_hedgehog__glu_gated_reglu__prompt'

def setup_inputs():

    _w = (lambda a: (lambda t: t.to(torch.bfloat16) if t.is_floating_point() else t)(torch.as_tensor(a)))
    def _A_setup():
        B, S, D, H = 1, 2048, 512, 32
        Dh = D // H
        return {
            "x": _w((lambda *s: torch.randn(*s, dtype=torch.bfloat16) * 0.05)(B, S, D)),
            "wqkv": _w((lambda *s: torch.randn(*s, dtype=torch.bfloat16) * 0.2)(D, 3 * D)),
            "w_phi": _w((lambda *s: torch.randn(*s, dtype=torch.bfloat16) * 0.2)(H, Dh, Dh) * (Dh ** -0.5)),
            "wo": _w((lambda *s: torch.randn(*s, dtype=torch.bfloat16) * 0.05)(D, D)),
        }
    _A_in = _A_setup()

    def _B_setup():
        B, S, D, F = 1, 2048, 512, 1792
        return {
            "x": _w((lambda *s: torch.randn(*s, dtype=torch.bfloat16) * 0.05)(B, S, D)),
            "W_gate": _w((lambda *s: torch.randn(*s, dtype=torch.bfloat16) * 0.4)(D, F) * (2.0 / D) ** 0.5),
            "W_up": _w((lambda *s: torch.randn(*s, dtype=torch.bfloat16) * 0.4)(D, F) * (2.0 / D) ** 0.5),
            "W_down": _w((lambda *s: torch.randn(*s, dtype=torch.bfloat16) * 0.4)(F, D) * (1.0 / F) ** 0.5),
        }
    _B_in = _B_setup()

    return {
        "A_x": _A_in["x"],
        "A_wqkv": _A_in["wqkv"],
        "A_w_phi": _A_in["w_phi"],
        "A_wo": _A_in["wo"],
        "B_x": _B_in["x"],
        "B_W_gate": _B_in["W_gate"],
        "B_W_up": _B_in["W_up"],
        "B_W_down": _B_in["W_down"],
    }

def reference(A_x, A_wqkv, A_w_phi, A_wo, B_x, B_W_gate, B_W_up, B_W_down):
    def _A_ref(x, wqkv, w_phi, wo):
        B, S, D = x.shape
        H = 32; Dh = D // H
        qkv = (lambda x, *d: x.permute(*d))((x @ wqkv).reshape(B, S, 3, H, Dh), 2, 0, 3, 1, 4)
        q, k, v = qkv[0], qkv[1], qkv[2]
        pq = torch.einsum("bhsd,hdf->bhsf", q, w_phi)
        pk = torch.einsum("bhsd,hdf->bhsf", k, w_phi)
        phi_q = torch.concatenate([_softmax(pq, axis=-1), _softmax(-pq, axis=-1)], axis=-1)
        phi_k = torch.concatenate([_softmax(pk, axis=-1), _softmax(-pk, axis=-1)], axis=-1)
        kv = torch.einsum("bhsf,bhsd->bhfd", phi_k, v)
        z  = torch.einsum("bhsf->bhf", phi_k)
        num = torch.einsum("bhqf,bhfd->bhqd", phi_q, kv)
        den = torch.einsum("bhqf,bhf->bhq", phi_q, z)[..., None] + 1e-6
        o = num / den
        return (lambda x, *d: x.permute(*d))(o, 0, 2, 1, 3).reshape(B, S, D) @ wo

    def _B_ref(x, W_gate, W_up, W_down):
        gate = torch.einsum("bsd,df->bsf", x, W_gate)
        up = torch.einsum("bsd,df->bsf", x, W_up)
        gate = gate * (lambda x, dt: x.to(dt))(gate > 0, gate.dtype)
        h = gate * up
        return torch.einsum("bsf,fd->bsd", h, W_down)

    x = A_x
    h = x + _A_ref(_layernorm(x, axis=-1), A_wqkv, A_w_phi, A_wo)
    h2 = h + _B_ref(_layernorm(h, axis=-1), B_W_gate, B_W_up, B_W_down)
    return h2
```

```cpp
#include <cuda_runtime.h>
#include <cuda_bf16.h>
#include <cuda.h>
#include <stdint.h>

namespace {

__device__ __forceinline__ uint64_t desc64(uint32_t lo) { return 0x4000004000000000ull | lo; }
template<int OB> __device__ __forceinline__ void wgmma_rk_n64(float* d, const uint32_t* a, uint32_t db, int sc) {
    asm volatile("{\n.reg .pred p;\n.reg .b64 rb;\nsetp.ne.b32 p, %37, 0;\n"
        "add.s64 rb, %36, %38;\n"
        "wgmma.mma_async.sync.aligned.m64n64k16.f32.bf16.bf16 {%0, %1, %2, %3, %4, %5, %6, %7, %8, %9, %10, %11, %12, %13, %14, %15, %16, %17, %18, %19, %20, %21, %22, %23, %24, %25, %26, %27, %28, %29, %30, %31}, {%32, %33, %34, %35}, rb, p, 1, 1, 0;\n}"
        : "+f"(d[0]), "+f"(d[1]), "+f"(d[2]), "+f"(d[3]), "+f"(d[4]), "+f"(d[5]), "+f"(d[6]), "+f"(d[7]), "+f"(d[8]), "+f"(d[9]), "+f"(d[10]), "+f"(d[11]), "+f"(d[12]), "+f"(d[13]), "+f"(d[14]), "+f"(d[15]), "+f"(d[16]), "+f"(d[17]), "+f"(d[18]), "+f"(d[19]), "+f"(d[20]), "+f"(d[21]), "+f"(d[22]), "+f"(d[23]), "+f"(d[24]), "+f"(d[25]), "+f"(d[26]), "+f"(d[27]), "+f"(d[28]), "+f"(d[29]), "+f"(d[30]), "+f"(d[31])
        : "r"(a[0]), "r"(a[1]), "r"(a[2]), "r"(a[3]), "l"(desc64(db)), "r"(sc), "n"(OB));
}
template<int OB> __device__ __forceinline__ void wgmma_rs_n64(float* d, const uint32_t* a, uint32_t db, int sc) {
    asm volatile("{\n.reg .pred p;\n.reg .b64 rb;\nsetp.ne.b32 p, %37, 0;\n"
        "add.s64 rb, %36, %38;\n"
        "wgmma.mma_async.sync.aligned.m64n64k16.f32.bf16.bf16 {%0, %1, %2, %3, %4, %5, %6, %7, %8, %9, %10, %11, %12, %13, %14, %15, %16, %17, %18, %19, %20, %21, %22, %23, %24, %25, %26, %27, %28, %29, %30, %31}, {%32, %33, %34, %35}, rb, p, 1, 1, 1;\n}"
        : "+f"(d[0]), "+f"(d[1]), "+f"(d[2]), "+f"(d[3]), "+f"(d[4]), "+f"(d[5]), "+f"(d[6]), "+f"(d[7]), "+f"(d[8]), "+f"(d[9]), "+f"(d[10]), "+f"(d[11]), "+f"(d[12]), "+f"(d[13]), "+f"(d[14]), "+f"(d[15]), "+f"(d[16]), "+f"(d[17]), "+f"(d[18]), "+f"(d[19]), "+f"(d[20]), "+f"(d[21]), "+f"(d[22]), "+f"(d[23]), "+f"(d[24]), "+f"(d[25]), "+f"(d[26]), "+f"(d[27]), "+f"(d[28]), "+f"(d[29]), "+f"(d[30]), "+f"(d[31])
        : "r"(a[0]), "r"(a[1]), "r"(a[2]), "r"(a[3]), "l"(desc64(db)), "r"(sc), "n"(OB));
}
template<int OB> __device__ __forceinline__ void wgmma_rs_n72(float* d, const uint32_t* a, uint32_t db, int sc) {
    asm volatile("{\n.reg .pred p;\n.reg .b64 rb;\nsetp.ne.b32 p, %41, 0;\n"
        "add.s64 rb, %40, %42;\n"
        "wgmma.mma_async.sync.aligned.m64n72k16.f32.bf16.bf16 {%0, %1, %2, %3, %4, %5, %6, %7, %8, %9, %10, %11, %12, %13, %14, %15, %16, %17, %18, %19, %20, %21, %22, %23, %24, %25, %26, %27, %28, %29, %30, %31, %32, %33, %34, %35}, {%36, %37, %38, %39}, rb, p, 1, 1, 1;\n}"
        : "+f"(d[0]), "+f"(d[1]), "+f"(d[2]), "+f"(d[3]), "+f"(d[4]), "+f"(d[5]), "+f"(d[6]), "+f"(d[7]), "+f"(d[8]), "+f"(d[9]), "+f"(d[10]), "+f"(d[11]), "+f"(d[12]), "+f"(d[13]), "+f"(d[14]), "+f"(d[15]), "+f"(d[16]), "+f"(d[17]), "+f"(d[18]), "+f"(d[19]), "+f"(d[20]), "+f"(d[21]), "+f"(d[22]), "+f"(d[23]), "+f"(d[24]), "+f"(d[25]), "+f"(d[26]), "+f"(d[27]), "+f"(d[28]), "+f"(d[29]), "+f"(d[30]), "+f"(d[31]), "+f"(d[32]), "+f"(d[33]), "+f"(d[34]), "+f"(d[35])
        : "r"(a[0]), "r"(a[1]), "r"(a[2]), "r"(a[3]), "l"(desc64(db)), "r"(sc), "n"(OB));
}
template<int OA, int OB> __device__ __forceinline__ void wgmma_ss_n224(float* d, uint32_t da, uint32_t db, int sc) {
    asm volatile("{\n.reg .pred p;\n.reg .b64 ra, rb;\nsetp.ne.b32 p, %114, 0;\n"
        "add.s64 ra, %112, %115;\nadd.s64 rb, %113, %116;\n"
        "wgmma.mma_async.sync.aligned.m64n224k16.f32.bf16.bf16 {%0, %1, %2, %3, %4, %5, %6, %7, %8, %9, %10, %11, %12, %13, %14, %15, %16, %17, %18, %19, %20, %21, %22, %23, %24, %25, %26, %27, %28, %29, %30, %31, %32, %33, %34, %35, %36, %37, %38, %39, %40, %41, %42, %43, %44, %45, %46, %47, %48, %49, %50, %51, %52, %53, %54, %55, %56, %57, %58, %59, %60, %61, %62, %63, %64, %65, %66, %67, %68, %69, %70, %71, %72, %73, %74, %75, %76, %77, %78, %79, %80, %81, %82, %83, %84, %85, %86, %87, %88, %89, %90, %91, %92, %93, %94, %95, %96, %97, %98, %99, %100, %101, %102, %103, %104, %105, %106, %107, %108, %109, %110, %111}, ra, rb, p, 1, 1, 0, 1;\n}"
        : "+f"(d[0]), "+f"(d[1]), "+f"(d[2]), "+f"(d[3]), "+f"(d[4]), "+f"(d[5]), "+f"(d[6]), "+f"(d[7]), "+f"(d[8]), "+f"(d[9]), "+f"(d[10]), "+f"(d[11]), "+f"(d[12]), "+f"(d[13]), "+f"(d[14]), "+f"(d[15]), "+f"(d[16]), "+f"(d[17]), "+f"(d[18]), "+f"(d[19]), "+f"(d[20]), "+f"(d[21]), "+f"(d[22]), "+f"(d[23]), "+f"(d[24]), "+f"(d[25]), "+f"(d[26]), "+f"(d[27]), "+f"(d[28]), "+f"(d[29]), "+f"(d[30]), "+f"(d[31]), "+f"(d[32]), "+f"(d[33]), "+f"(d[34]), "+f"(d[35]), "+f"(d[36]), "+f"(d[37]), "+f"(d[38]), "+f"(d[39]), "+f"(d[40]), "+f"(d[41]), "+f"(d[42]), "+f"(d[43]), "+f"(d[44]), "+f"(d[45]), "+f"(d[46]), "+f"(d[47]), "+f"(d[48]), "+f"(d[49]), "+f"(d[50]), "+f"(d[51]), "+f"(d[52]), "+f"(d[53]), "+f"(d[54]), "+f"(d[55]), "+f"(d[56]), "+f"(d[57]), "+f"(d[58]), "+f"(d[59]), "+f"(d[60]), "+f"(d[61]), "+f"(d[62]), "+f"(d[63]), "+f"(d[64]), "+f"(d[65]), "+f"(d[66]), "+f"(d[67]), "+f"(d[68]), "+f"(d[69]), "+f"(d[70]), "+f"(d[71]), "+f"(d[72]), "+f"(d[73]), "+f"(d[74]), "+f"(d[75]), "+f"(d[76]), "+f"(d[77]), "+f"(d[78]), "+f"(d[79]), "+f"(d[80]), "+f"(d[81]), "+f"(d[82]), "+f"(d[83]), "+f"(d[84]), "+f"(d[85]), "+f"(d[86]), "+f"(d[87]), "+f"(d[88]), "+f"(d[89]), "+f"(d[90]), "+f"(d[91]), "+f"(d[92]), "+f"(d[93]), "+f"(d[94]), "+f"(d[95]), "+f"(d[96]), "+f"(d[97]), "+f"(d[98]), "+f"(d[99]), "+f"(d[100]), "+f"(d[101]), "+f"(d[102]), "+f"(d[103]), "+f"(d[104]), "+f"(d[105]), "+f"(d[106]), "+f"(d[107]), "+f"(d[108]), "+f"(d[109]), "+f"(d[110]), "+f"(d[111])
        : "l"(desc64(da)), "l"(desc64(db)), "r"(sc), "n"(OA), "n"(OB));
}
template<int OA, int OB> __device__ __forceinline__ void wgmma_st_n72(float* d, uint32_t da, uint32_t db, int sc) {
    asm volatile("{\n.reg .pred p;\n.reg .b64 ra, rb;\nsetp.ne.b32 p, %38, 0;\n"
        "add.s64 ra, %36, %39;\nadd.s64 rb, %37, %40;\n"
        "wgmma.mma_async.sync.aligned.m64n72k16.f32.bf16.bf16 {%0, %1, %2, %3, %4, %5, %6, %7, %8, %9, %10, %11, %12, %13, %14, %15, %16, %17, %18, %19, %20, %21, %22, %23, %24, %25, %26, %27, %28, %29, %30, %31, %32, %33, %34, %35}, ra, rb, p, 1, 1, 1, 1;\n}"
        : "+f"(d[0]), "+f"(d[1]), "+f"(d[2]), "+f"(d[3]), "+f"(d[4]), "+f"(d[5]), "+f"(d[6]), "+f"(d[7]), "+f"(d[8]), "+f"(d[9]), "+f"(d[10]), "+f"(d[11]), "+f"(d[12]), "+f"(d[13]), "+f"(d[14]), "+f"(d[15]), "+f"(d[16]), "+f"(d[17]), "+f"(d[18]), "+f"(d[19]), "+f"(d[20]), "+f"(d[21]), "+f"(d[22]), "+f"(d[23]), "+f"(d[24]), "+f"(d[25]), "+f"(d[26]), "+f"(d[27]), "+f"(d[28]), "+f"(d[29]), "+f"(d[30]), "+f"(d[31]), "+f"(d[32]), "+f"(d[33]), "+f"(d[34]), "+f"(d[35])
        : "l"(desc64(da)), "l"(desc64(db)), "r"(sc), "n"(OA), "n"(OB));
}


constexpr uint32_t OFF_RING = 131072, OFF_ONES = 229376, OFF_BAR = 231424, OFF_RM = OFF_BAR + 512, OFF_RM4 = OFF_BAR + 768;
constexpr uint32_t SMEM_TOTAL = 232448;
constexpr uint32_t B_A = 0, B_PP = 128, B_FULL = 192, B_EMPTY = 256, B_F0 = 304, B_FQ = 312, B_FP = 320, B_F2 = 336, B_F3 = 352, B_TB = 368,
                   B_KVB = 384, B_F1 = 392, B_ZR = 400, B_BD = 408, B_FX = 424, B_SS = 440, B_GO = 448, B_XC = 456;
constexpr uint64_t CNT_GROUP = 0x122211111111ull, CNT_EXTRA = 0x118111122344ull;
constexpr int SPIN_LIMIT = 1 << 18;

struct Scratch {
    uint4 xch[4][128][1024];
    float4 kv[8][768];
    unsigned row[128][288];
    unsigned cnt;
};
__device__ unsigned char g_scratch[sizeof(Scratch) + 131072];
struct Ptrs { const __nv_bfloat16 *x, *wqkv, *wphi, *wo; Scratch* s; };
struct Params {
    CUtensorMap tx, tqkv, two, tg3, tgh, tu3, tuh, td192, td32, tout;
    const __nv_bfloat16* wf[3];
};

__device__ __forceinline__ uint32_t smem_u32(const void* p) { return (uint32_t)__cvta_generic_to_shared(p); }
__device__ __forceinline__ void mbar_init(uint32_t bar, uint32_t cnt) { asm volatile("mbarrier.init.shared::cta.b64 [%0], %1;" :: "r"(bar), "r"(cnt) : "memory"); }
__device__ __forceinline__ void mbar_expect_tx(uint32_t bar, uint32_t bytes) { asm volatile("mbarrier.arrive.expect_tx.shared::cta.b64 _, [%0], %1;" :: "r"(bar), "r"(bytes) : "memory"); }
__device__ __forceinline__ void mbar_wait(uint32_t bar, uint32_t parity) {
    asm volatile("{\n.reg .pred p;\nLAB_WAIT:\nmbarrier.try_wait.parity.shared::cta.b64 p, [%0], %1;\n@!p bra LAB_WAIT;\n}" :: "r"(bar), "r"(parity) : "memory");
}
__device__ __forceinline__ bool mbar_test(uint32_t bar, uint32_t parity) {
    uint32_t ok;
    asm volatile("{\n.reg .pred p;\nmbarrier.test_wait.parity.shared::cta.b64 p, [%1], %2;\nselp.u32 %0, 1, 0, p;\n}" : "=r"(ok) : "r"(bar), "r"(parity) : "memory");
    return ok;
}
__device__ __forceinline__ void mbar_arrive(uint32_t bar) { asm volatile("mbarrier.arrive.shared::cta.b64 _, [%0];" :: "r"(bar) : "memory"); }
__device__ __forceinline__ void mbar_arrive_cl(uint32_t bar) { asm volatile("mbarrier.arrive.shared::cluster.b64 _, [%0];" :: "r"(bar) : "memory"); }
__device__ __forceinline__ uint32_t mapa(uint32_t a, uint32_t cta) { uint32_t r; asm("mapa.shared::cluster.u32 %0, %1, %2;" : "=r"(r) : "r"(a), "r"(cta)); return r; }
__device__ __forceinline__ void bar_sync(int id, int n) { asm volatile("bar.sync %0, %1;" :: "r"(id), "r"(n) : "memory"); }
__device__ __forceinline__ void bar_arrive(int id, int n) { asm volatile("bar.arrive %0, %1;" :: "r"(id), "r"(n) : "memory"); }
__device__ __forceinline__ bool bar_and(int id, int n, bool v) {
    uint32_t r;
    asm volatile("{\n.reg .pred p, q;\nsetp.ne.u32 p, %3, 0;\nbar.red.and.pred q, %1, %2, p;\nselp.u32 %0, 1, 0, q;\n}" : "=r"(r) : "r"(id), "r"(n), "r"((uint32_t)v) : "memory");
    return r;
}
__device__ __forceinline__ void fence_async_smem() { asm volatile("fence.proxy.async.shared::cta;" ::: "memory"); }
__device__ __forceinline__ void fence_gpu() { asm volatile("fence.acq_rel.gpu;" ::: "memory"); }
__device__ __forceinline__ void tma2d(uint32_t dst, const CUtensorMap* m, uint32_t bar, int c0, int c1) {
    asm volatile("cp.async.bulk.tensor.2d.shared::cluster.global.mbarrier::complete_tx::bytes [%0], [%1, {%3, %4}], [%2];" :: "r"(dst), "l"(m), "r"(bar), "r"(c0), "r"(c1) : "memory");
}
__device__ __forceinline__ void tma3d(uint32_t dst, const CUtensorMap* m, uint32_t bar, int c0, int c1, int c2) {
    asm volatile("cp.async.bulk.tensor.3d.shared::cluster.global.mbarrier::complete_tx::bytes [%0], [%1, {%3, %4, %5}], [%2];" :: "r"(dst), "l"(m), "r"(bar), "r"(c0), "r"(c1), "r"(c2) : "memory");
}
__device__ __forceinline__ void tma2d_store(const CUtensorMap* m, uint32_t src, int c0, int c1) {
    asm volatile("cp.async.bulk.tensor.2d.global.shared::cta.bulk_group [%0, {%2, %3}], [%1];" :: "l"(m), "r"(src), "r"(c0), "r"(c1) : "memory");
}
__device__ __forceinline__ void bulk_load_mc(uint32_t dst, const void* src, uint32_t bytes, uint32_t bar) {
    asm volatile("cp.async.bulk.shared::cluster.global.mbarrier::complete_tx::bytes.multicast::cluster [%0], [%1], %2, [%3], %4;" :: "r"(dst), "l"(src), "r"(bytes), "r"(bar), "h"((uint16_t)3) : "memory");
}
__device__ __forceinline__ void bulk_store(void* dst, uint32_t src, uint32_t bytes) {
    asm volatile("cp.async.bulk.global.shared::cta.bulk_group [%0], [%1], %2;" :: "l"(dst), "r"(src), "r"(bytes) : "memory");
}
__device__ __forceinline__ void bulk_push(uint32_t dst, uint32_t src, uint32_t bytes, uint32_t bar) {
    asm volatile("cp.async.bulk.shared::cluster.shared::cta.mbarrier::complete_tx::bytes [%0], [%1], %2, [%3];" :: "r"(dst), "r"(src), "r"(bytes), "r"(bar) : "memory");
}
__device__ __forceinline__ void bulk_commit() { asm volatile("cp.async.bulk.commit_group;" ::: "memory"); }
__device__ __forceinline__ void bulk_wait0() { asm volatile("cp.async.bulk.wait_group 0;" ::: "memory"); }
__device__ __forceinline__ void bulk_wait0_read() { asm volatile("cp.async.bulk.wait_group.read 0;" ::: "memory"); }
__device__ __forceinline__ void l2_prefetch(const void* p, uint32_t bytes) { asm volatile("cp.async.bulk.prefetch.L2.global [%0], %1;" :: "l"(p), "r"(bytes) : "memory"); }
__device__ __forceinline__ void tmap_prefetch(const CUtensorMap* m) { asm volatile("prefetch.tensormap [%0];" :: "l"(m) : "memory"); }
__device__ __forceinline__ void wg_fence() { asm volatile("wgmma.fence.sync.aligned;" ::: "memory"); }
__device__ __forceinline__ void wg_commit() { asm volatile("wgmma.commit_group.sync.aligned;" ::: "memory"); }
template<int N> __device__ __forceinline__ void wg_wait() { asm volatile("wgmma.wait_group.sync.aligned %0;" :: "n"(N) : "memory"); }
template<int V> struct IC { static constexpr int v = V; };
template<int... I> struct Seq {};
template<int N, int... I> struct MkSeq : MkSeq<N - 1, N - 1, I...> {};
template<int... I> struct MkSeq<0, I...> { typedef Seq<I...> type; };
template<int N> using IdxSeq = typename MkSeq<N>::type;
template<class F, int... I> __device__ __forceinline__ void static_for_impl(F& f, Seq<I...>) { (f(IC<I>{}), ...); }
__device__ __forceinline__ uint32_t mkdesc(uint32_t addr, uint32_t lbo) { return ((addr & 0x3FFFF) >> 4) | ((lbo >> 4) << 16); }
template<int N, class F> __device__ __forceinline__ void static_for(F&& f) { static_for_impl(f, IdxSeq<N>{}); }
template<int N> __device__ __forceinline__ void reg_fence(float* d) {
    #pragma unroll
    for (int i = 0; i < N; i++) asm volatile("" : "+f"(d[i]) :: "memory");
}
template<int N> __device__ __forceinline__ void keep_live(uint32_t* d) {
    #pragma unroll
    for (int i = 0; i < N; i++) asm volatile("" : "+r"(d[i]) :: "memory");
}
__device__ __forceinline__ uint32_t pack2(float lo, float hi) { uint32_t r; asm("cvt.rn.bf16x2.f32 %0, %1, %2;" : "=r"(r) : "f"(hi), "f"(lo)); return r; }
__device__ __forceinline__ uint32_t pack2_relu(float lo, float hi) { uint32_t r; asm("cvt.rn.relu.bf16x2.f32 %0, %1, %2;" : "=r"(r) : "f"(hi), "f"(lo)); return r; }
__device__ __forceinline__ uint32_t mul2(uint32_t a, uint32_t b) { uint32_t r; asm("mul.rn.bf16x2 %0, %1, %2;" : "=r"(r) : "r"(a), "r"(b)); return r; }
__device__ __forceinline__ uint32_t add2(uint32_t a, uint32_t b) { uint32_t r; asm("add.rn.bf16x2 %0, %1, %2;" : "=r"(r) : "r"(a), "r"(b)); return r; }
__device__ __forceinline__ uint32_t sub2(uint32_t a, uint32_t b) { uint32_t r; asm("sub.rn.bf16x2 %0, %1, %2;" : "=r"(r) : "r"(a), "r"(b)); return r; }
__device__ __forceinline__ float bf_lo(uint32_t v) { return __uint_as_float(v << 16); }
__device__ __forceinline__ float bf_hi(uint32_t v) { return __uint_as_float(v & 0xffff0000u); }
__device__ __forceinline__ float ex2(float x) { float r; asm("ex2.approx.ftz.f32 %0, %1;" : "=f"(r) : "f"(x)); return r; }
__device__ __forceinline__ float rsq(float x) { float r; asm("rsqrt.approx.ftz.f32 %0, %1;" : "=f"(r) : "f"(x)); return r; }
__device__ __forceinline__ float rcp(float x) { float r; asm("rcp.approx.ftz.f32 %0, %1;" : "=f"(r) : "f"(x)); return r; }
__device__ __forceinline__ void ldsm4(uint32_t* r, uint32_t a) {
    asm volatile("ldmatrix.sync.aligned.m8n8.x4.shared.b16 {%0,%1,%2,%3}, [%4];" : "=r"(r[0]), "=r"(r[1]), "=r"(r[2]), "=r"(r[3]) : "r"(a) : "memory");
}
__device__ __forceinline__ void stsm4(uint32_t a, uint32_t r0, uint32_t r1, uint32_t r2, uint32_t r3) {
    asm volatile("stmatrix.sync.aligned.m8n8.x4.shared.b16 [%0], {%1,%2,%3,%4};" :: "r"(a), "r"(r0), "r"(r1), "r"(r2), "r"(r3) : "memory");
}
__device__ __forceinline__ void ldsm4t(uint32_t* r, uint32_t a) {
    asm volatile("ldmatrix.sync.aligned.m8n8.x4.trans.shared.b16 {%0,%1,%2,%3}, [%4];" : "=r"(r[0]), "=r"(r[1]), "=r"(r[2]), "=r"(r[3]) : "r"(a) : "memory");
}
__device__ __forceinline__ void stsm4t(uint32_t a, uint32_t r0, uint32_t r1, uint32_t r2, uint32_t r3) {
    asm volatile("stmatrix.sync.aligned.m8n8.x4.trans.shared.b16 [%0], {%1,%2,%3,%4};" :: "r"(a), "r"(r0), "r"(r1), "r"(r2), "r"(r3) : "memory");
}
__device__ __forceinline__ void sts4(uint32_t a, uint32_t r0, uint32_t r1, uint32_t r2, uint32_t r3) {
    asm volatile("st.shared.v4.b32 [%0], {%1,%2,%3,%4};" :: "r"(a), "r"(r0), "r"(r1), "r"(r2), "r"(r3) : "memory");
}
__device__ __forceinline__ void lds4(uint32_t* r, uint32_t a) {
    asm volatile("ld.shared.v4.b32 {%0,%1,%2,%3}, [%4];" : "=r"(r[0]), "=r"(r[1]), "=r"(r[2]), "=r"(r[3]) : "r"(a) : "memory");
}
__device__ __forceinline__ void mma16816(float* c, const uint32_t* a, uint32_t b0, uint32_t b1) {
    asm volatile("mma.sync.aligned.m16n8k16.row.col.f32.bf16.bf16.f32 {%0,%1,%2,%3}, {%4,%5,%6,%7}, {%8,%9}, {%0,%1,%2,%3};"
                 : "+f"(c[0]), "+f"(c[1]), "+f"(c[2]), "+f"(c[3]) : "r"(a[0]), "r"(a[1]), "r"(a[2]), "r"(a[3]), "r"(b0), "r"(b1));
}
__device__ __forceinline__ uint32_t ld_rlx(const unsigned* p) { uint32_t v; asm volatile("ld.relaxed.gpu.global.u32 %0, [%1];" : "=r"(v) : "l"(p) : "memory"); return v; }
__device__ __forceinline__ void st_rlx(unsigned* p, uint32_t v) { asm volatile("st.relaxed.gpu.global.u32 [%0], %1;" :: "l"(p), "r"(v) : "memory"); }
__device__ __forceinline__ void ld_rlx128(uint32_t* r, const void* p) {
    asm volatile("ld.relaxed.gpu.global.v4.b32 {%0,%1,%2,%3}, [%4];" : "=r"(r[0]), "=r"(r[1]), "=r"(r[2]), "=r"(r[3]) : "l"(p) : "memory");
}
__device__ __forceinline__ void st_rlx128(void* p, uint32_t r0, uint32_t r1, uint32_t r2, uint32_t r3) {
    asm volatile("st.relaxed.gpu.global.v4.b32 [%0], {%1,%2,%3,%4};" :: "l"(p), "r"(r0), "r"(r1), "r"(r2), "r"(r3) : "memory");
}
__device__ __forceinline__ void red_add(unsigned* p) { asm volatile("red.relaxed.gpu.global.add.u32 [%0], 1;" :: "l"(p) : "memory"); }
__device__ __forceinline__ void red_f4(float4* p, float a, float b, float c) { asm volatile("red.relaxed.gpu.global.add.v4.f32 [%0], {%1, %2, %3, %4};" :: "l"(p), "f"(a), "f"(b), "f"(c), "f"(1.0f) : "memory"); }
__device__ __forceinline__ bool elect_one() { uint32_t p; asm volatile("{\n.reg .pred P;\nelect.sync _|P, 0xffffffff;\nselp.u32 %0, 1, 0, P;\n}" : "=r"(p)); return p; }
__device__ __forceinline__ void sts1(uint32_t a, uint32_t v) { asm volatile("st.shared.u32 [%0], %1;" :: "r"(a), "r"(v) : "memory"); }
__device__ __forceinline__ uint32_t lds1(uint32_t a) { uint32_t v; asm volatile("ld.shared.u32 %0, [%1];" : "=r"(v) : "r"(a) : "memory"); return v; }
__device__ __forceinline__ void mma1688(float* c, uint32_t a0, uint32_t a1, uint32_t b) {
    asm volatile("mma.sync.aligned.m16n8k8.row.col.f32.bf16.bf16.f32 {%0,%1,%2,%3}, {%4,%5}, {%6}, {%0,%1,%2,%3};"
                 : "+f"(c[0]), "+f"(c[1]), "+f"(c[2]), "+f"(c[3]) : "r"(a0), "r"(a1), "r"(b));
}
__device__ __forceinline__ void poll_async(uint32_t dst, const void* src) { asm volatile("cp.async.cg.shared.global [%0], [%1], 16;" :: "r"(dst), "l"(src) : "memory"); }
__device__ __forceinline__ void poll_drain() { asm volatile("cp.async.wait_all;" ::: "memory"); }
__device__ __forceinline__ uint32_t pin(uint32_t v) { return __shfl_xor_sync(~0u, v, 0); }
__device__ __forceinline__ void anchor(uint32_t& a) { asm volatile("{\n.reg .u32 t;\nmov.u32 t, %%clock;\nxor.b32 %0, %0, t;\n}" : "+r"(a) :: "memory"); }
__device__ __forceinline__ void cluster_wait() { asm volatile("barrier.cluster.wait.aligned;" ::: "memory"); }
__device__ __forceinline__ void poll_ge(const unsigned* p, uint32_t target) {
    int it = 0;
    #pragma unroll 1
    while ((int)(ld_rlx(p) - target) < 0) { if (++it > SPIN_LIMIT) break; }
}

struct DualExp {
    float c0, c1, k0, k1, sp0, sm0, sp1, sm1;
    __device__ __forceinline__ void init(const float* p, float* t) {
        float mx[4], mn[4];
        #pragma unroll
        for (int u = 0; u < 4; u++) mx[u] = mn[u] = p[u];
        #pragma unroll
        for (int v = 4; v < 32; v++) { mx[v & 3] = fmaxf(mx[v & 3], p[v]); mn[v & 3] = fminf(mn[v & 3], p[v]); }
        const float b0 = -fmaxf(mx[0], mx[1]) * c0, b1 = -fmaxf(mx[2], mx[3]) * c1;
        k0 = fmaf(fminf(mn[0], mn[1]), c0, b0); k1 = fmaf(fminf(mn[2], mn[3]), c1, b1);
        #pragma unroll
        for (int v = 0; v < 32; v++) t[v] = (v & 2) ? fmaf(p[v], c1, b1) : fmaf(p[v], c0, b0);
        sp0 = sm0 = sp1 = sm1 = 0.f;
    }
    __device__ __forceinline__ void unit(const float* t, uint32_t* e) {
        const float a0 = ex2(t[0]), a1 = ex2(t[1]), a2 = ex2(t[2]), a3 = ex2(t[3]);
        const float b0 = ex2(k0 - t[0]), b1 = ex2(k0 - t[1]), b2 = ex2(k1 - t[2]), b3 = ex2(k1 - t[3]);
        sp0 += a0 + a1; sp1 += a2 + a3; sm0 += b0 + b1; sm1 += b2 + b3;
        e[0] = pack2(a0, a1); e[1] = pack2(a2, a3); e[2] = pack2(b0, b1); e[3] = pack2(b2, b3);
    }
};

__device__ __forceinline__ uint32_t stale(uint32_t a, uint32_t b, uint32_t c, uint32_t d, uint32_t t) {
    uint32_t x, y, r;
    asm("lop3.b32 %0, %1, %2, %3, 0x7e;" : "=r"(x) : "r"(a), "r"(b), "r"(t));
    asm("lop3.b32 %0, %1, %2, %3, 0x7e;" : "=r"(y) : "r"(c), "r"(d), "r"(t));
    asm("lop3.b32 %0, %1, %2, 1, 0xa8;" : "=r"(r) : "r"(x), "r"(y));
    return r;
}
__device__ __forceinline__ void row_store(unsigned* p, float a, float b, int q) {
    a += __shfl_xor_sync(~0u, a, 1); b += __shfl_xor_sync(~0u, b, 1);
    a += __shfl_xor_sync(~0u, a, 2); b += __shfl_xor_sync(~0u, b, 2);
    if (q < 2) st_rlx(p + q * 8, __float_as_uint(q ? b : a) | 1u);
}
__device__ __forceinline__ void tags_load(uint32_t* t, uint32_t a) {
    t[0] = lds1(a); t[1] = lds1(a ^ 16); t[2] = lds1(a + 1024); t[3] = lds1((a ^ 16) + 1024);
}
__device__ __forceinline__ void fetch(uint32_t dst, const uint4* src) {
    #pragma unroll
    for (int b = 0; b < 4; b++) poll_async(dst + b * 512, src + b * 32);
}
__device__ __forceinline__ void settle(uint32_t dst, const uint4* src, uint32_t tags) {
    #pragma unroll 1
    for (int it = 0; it < SPIN_LIMIT; it++) {
        poll_drain();
        __syncwarp();
        uint32_t t[4];
        tags_load(t, tags);
        if (!__any_sync(~0u, stale(t[0], t[1], t[2], t[3], 1u))) break;
        fetch(dst, src);
    }
    fence_async_smem();
    __syncwarp();
}

__global__ void __cluster_dims__(2, 1, 1) __launch_bounds__(384, 1) fused_kernel(const Ptrs Q, const __grid_constant__ Params P) {
    extern __shared__ __align__(1024) char smraw[];
    const uint32_t base = smem_u32(smraw);
    const uint32_t ring = base + OFF_RING, bars = base + OFF_BAR;
    const int tid = threadIdx.x, warp = __shfl_sync(~0u, tid >> 5, 0), lane = tid & 31;
    const int cta = blockIdx.x, j = cta & 7, i = cta >> 3, e = j & 1, p = j >> 1;
    if (tid >= 128 && tid < 160)
        asm volatile("prefetch.global.L2 [%0];" :: "l"(Q.x + (cta * 16 + (tid & 15)) * 512 + ((tid - 128) >> 4) * 64) : "memory");
    if (elect_one()) {
        if (warp == 0) {
            #pragma unroll
            for (int c = 0; c < 8; c++) {
                mbar_init(bars + B_A + c * 8, 1);
                asm volatile("fence.mbarrier_init.release.cluster;" ::: "memory");
                mbar_expect_tx(bars + B_A + c * 8, 16384);
                tma2d(base + (c ^ j) * 16384, &P.tx, bars + B_A + c * 8, c * 64, i * 128);
            }
        } else if (warp > 1) {
            #pragma unroll
            for (int u = 0; u < 4; u++) mbar_init(bars + warp * 32 + u * 8, (uint32_t)(CNT_GROUP >> (4 * warp)) & 7);
        } else tmap_prefetch(&P.tqkv);
        mbar_init(bars + B_KVB + warp * 8, (uint32_t)(CNT_EXTRA >> (4 * warp)) & 15);
        asm volatile("fence.mbarrier_init.release.cluster;" ::: "memory");
    }
    __syncwarp();
    if (warp >= 2 && warp < 8 && lane < 4) mbar_expect_tx(bars + warp * 32 + lane * 8, ((warp >> 1) - 1) * 8192);
    if (tid == 228) mbar_expect_tx(bars + B_SS, 512);
    asm volatile("barrier.cluster.arrive.relaxed.aligned;" ::: "memory");
    cluster_wait();
    constexpr uint32_t oBD = 24576, oKV = 90112, oZ = 122880;
    const uint32_t rbase = mapa(base, e ^ 1), rbars = rbase + OFF_BAR;

    if (warp >= 8) {
        asm volatile("setmaxnreg.dec.sync.aligned.u32 40;");
        if (warp == 8) {
            uint32_t sl = 0;
            #pragma unroll 1
            for (int st = 0; st < 14; st++) {
                const uint32_t fb = bars + B_FULL + sl * 8;
                if (st == 4) mbar_wait(bars + B_FULL, 0);
                if (st >= 6) mbar_wait(fb + (B_EMPTY - B_FULL), st >= 12);
                if (elect_one()) {
                    if (st >= 6) mbar_expect_tx(fb, 16384);
                    tma2d(ring + sl * 16384, st < 12 ? &P.tqkv : &P.two, fb, (st < 8 ? 512 + (st >> 2) * 512 : 0) + 64 * j, ((st < 12 ? 0 : p) ^ (st & 3)) * 128);
                    if (st == 8 || st == 9) l2_prefetch(P.wf[st - 8] + cta * 7168, 14336);
                }
                if (++sl == 6) sl = 0;
                if (st == 7) asm volatile("prefetch.global.L2 [%0];" :: "l"(Q.wqkv + (cta * 4 + (lane >> 3)) * 1536 + (lane & 7) * 64) : "memory");
            }
        } else if (warp == 11) {
            sts4(base + OFF_ONES + (lane >> 2) * 128 + (((lane >> 3) ^ 2 ^ ((lane >> 1) & 1)) << 5) + (lane & 1) * 16, 0u, 0u, 0u, 0u);
            const uint32_t target = (ld_rlx(&Q.s->cnt) & ~127u) + 128;
            uint4* kvz = (uint4*)&Q.s->kv[j][48 * i] + lane;
            uint4* rz = (uint4*)&Q.s->row[cta][0] + lane;
            const uint4 zero = make_uint4(0u, 0u, 0u, 0u);
            kvz[0] = zero; kvz[16] = zero; rz[0] = zero; rz[32] = zero; rz[40] = zero;
            __syncwarp();
            if (lane == 0) {
                fence_gpu(); red_add(&Q.s->cnt);
                sts1(base + OFF_RM4 + 16, (target >> 7) & 1);
                poll_ge(&Q.s->cnt, target); fence_gpu(); mbar_arrive(bars + B_ZR);
            }
            __syncwarp();
            mbar_wait(bars + B_XC, 0);
            if (lane < 16) mbar_expect_tx(bars + B_A + lane * 8, 8192);
        } else {
            const int k = (warp - 9) * 32 + lane, h = k >> 4;
            const uint4* src = (const uint4*)(Q.wphi + (64 * j + k) * 16);
            const uint4 w0 = __ldg(src), w1 = __ldg(src + 1);
            {
                const uint4* wr = (const uint4*)(Q.wo + (64 * j + 4 * i + h) * 512) + (lane & 15);
                uint32_t v[16];
                #pragma unroll
                for (int u = 0; u < 4; u++) *(uint4*)(v + 4 * u) = __ldg(wr + u * 16);
                float c[4] = {0.f, 0.f, 0.f, 0.f};
                #pragma unroll
                for (int u = 0; u < 4; u++) mma16816(c, v + 4 * u, 0x3f803f80u, 0x3f803f80u);
                float s = c[0] + c[2];
                s += __shfl_xor_sync(~0u, s, 4); s += __shfl_xor_sync(~0u, s, 8);
                if ((lane & 15) == 0) sts1(base + OFF_RM4 + h * 4, __float_as_uint(s * (1.f / 512.f)));
            }
            if (k < 16) sts4(base + OFF_ONES + k * 128 + (k & 7) * 16, 0x3f803f80u, 0x3f803f80u, 0x3f803f80u, 0x3f803f80u);
            if (elect_one()) {
                #pragma unroll
                for (int u = 0; u < 4; u++) tmap_prefetch(&P.two + (warp - 9) * 4 + u);
            }
            mbar_wait(bars + B_XC, 0);
            #pragma unroll 1
            for (int t = 0; t < 8; t++) sts4(base + oBD + k * 16 + t * 1024, 0u, 0u, 0u, 0u);
            bar_sync(5, 64);
            const uint32_t ww[8] = {w0.x, w0.y, w0.z, w0.w, w1.x, w1.y, w1.z, w1.w};
            const uint32_t a = base + oBD + k * 128 + ((k & 7) << 4) + h * 4;
            #pragma unroll
            for (int t = 0; t < 8; t++) sts1(a ^ (t << 4), ww[t]);
            fence_async_smem();
            __syncwarp();
            if (lane == 0) mbar_arrive(bars + B_BD);
            #pragma unroll 1
            for (int t = 0; t < 8; t++) { sts4(base + oKV + k * 16 + t * 1024, 0u, 0u, 0u, 0u); sts4(base + oKV + 16384 + k * 16 + t * 1024, 0u, 0u, 0u, 0u); }
            sts4(base + oZ + k * 128 + ((k & 7) << 4), 0u, 0u, 0u, 0u);
            sts4(base + oZ + k * 128 + (((k & 7) ^ 1) << 4), 0u, 0u, 0u, 0u);
            fence_async_smem();
            bar_sync(5, 64);
            if (lane == 0) mbar_arrive(bars + B_ZR);
            #pragma unroll 1
            for (int u = 0; u < 4; u++) {
                if (elect_one()) { bulk_store(&Q.s->xch[1][cta][(warp - 9) * 512 + u * 128], base + oKV, 2048); bulk_commit(); bulk_wait0(); }
            }
            if (elect_one()) fence_gpu();
        }
        {
            const int h = lane >> 3, g = (warp - 8) * 2 + ((lane >> 2) & 1), q = lane & 3, r7 = 2 * h + (g & 1);
            const float4* src = &Q.s->kv[j][h * 32 + g * 4 + q];
            const uint32_t ro = base + (16 * (g >> 1) + r7) * 128 + 4 * h, a1 = ro + oKV + ((q ^ r7) << 4);
            const uint32_t az = q < 2 ? ro + oZ + ((q ^ r7) << 4) : base + OFF_RM + (16 * h + 2 * g + (q & 1)) * 4;
            uint32_t v[24];
            int it = 0;
            bar_sync(2, 256);
            {
                const unsigned* cp = (const unsigned*)&Q.s->kv[j][256 + (warp - 8) * 40 + 7] + 3;
                #pragma unroll 1
                while (ld_rlx(cp) != 0x41800000u && ++it < SPIN_LIMIT) {}
            }
            #pragma unroll 1
            do {
                #pragma unroll
                for (int u = 0; u < 6; u++) ld_rlx128(v + u * 4, src + u * 128);
            } while (__any_sync(~0u, (v[3] & v[7] & v[11] & v[15] & v[19] & v[23]) != 0x41800000u) && ++it < 2 * SPIN_LIMIT);
            #pragma unroll
            for (int hf = 0; hf < 2; hf++) {
                const uint32_t* u = v + hf * 12;
                sts1(a1 + hf * 1024, pack2(__uint_as_float(u[0]), __uint_as_float(u[1])));
                sts1(a1 + hf * 1024 + 16384, pack2(__uint_as_float(u[2]), __uint_as_float(u[4])));
                sts1((a1 ^ 64) + hf * 1024, pack2(__uint_as_float(u[5]), __uint_as_float(u[6])));
                sts1((a1 ^ 64) + hf * 1024 + 16384, pack2(__uint_as_float(u[8]), __uint_as_float(u[9])));
            }
            sts1(az, q < 2 ? pack2(__uint_as_float(v[10]), 0.f) : v[10]);
            if (q < 2) sts1(az + 1024, pack2(__uint_as_float(v[22]), 0.f));
            fence_async_smem();
            __syncwarp();
            if (lane == 0) mbar_arrive(bars + B_KVB);
        }
        if (warp == 8) {
            const int fa = (224 * j + e * 32) >> 6;
            const int fh = e ? 224 * j : 224 * j + 192;
            uint32_t fb = bars + B_FULL + 2 * 8, dst = ring + 2 * 16384, ph = 1;
            #pragma unroll 1
            for (int st = 2; st < 4; st++) {
                mbar_wait(fb + (B_EMPTY - B_FULL), 1);
                if (elect_one()) { mbar_expect_tx(fb, 16384); tma2d(dst, &P.two, fb, 64 * j, (p ^ st) * 128); }
                fb += 8; dst += 16384;
            }
            #pragma unroll 1
            for (int pass = 0; pass < 2; pass++) {
                const CUtensorMap* m3 = pass ? &P.tu3 : &P.tg3;
                #pragma unroll 1
                for (int k = 0; k < 512; k += 32) {
                    const int kr = k ^ (k < 128 ? j * 64 : p * 128);
                    mbar_wait(fb + (B_EMPTY - B_FULL), ph);
                    if (elect_one()) {
                        mbar_expect_tx(fb, 14336);
                        tma3d(dst, m3, fb, 0, kr, fa);
                        tma2d(dst + 12288, m3 + 1, fb, fh, kr);
                    }
                    fb += 8; dst += 16384;
                    if (fb == bars + B_FULL + 48) { fb -= 48; dst -= 98304; ph ^= 1; }
                }
            }
            #pragma unroll 1
            for (int u = 0; u < 8; u++) {
                const int s = (0x76521403 >> (4 * u)) & 7;
                const int col = (j ^ (7 - s)) * 64, b = s < 5 ? s : s - 5;
                const uint32_t f2 = bars + (b < 3 ? B_FULL + b * 16 : B_FX - 24 + b * 8);
                const uint32_t d2 = base + (b < 3 ? b + 4 : b - 2) * 32768;
                if (b < 3) mbar_wait(bars + B_EMPTY + b * 16, s < 3);
                if (s < 3) mbar_wait(bars + B_EMPTY + b * 16 + 8, 1);
                if (elect_one()) {
                    mbar_expect_tx(f2, 28672);
                    tma2d(d2, &P.td192, f2, col, fa * 64);
                    tma2d(d2 + 24576, &P.td32, f2, col, fh);
                }
            }
        } else if (warp == 11) {
            const int w = lane & 1, sl = 2 + (lane & 6) + e, src_cta = cta ^ ((2 + (lane & 6)) & 7);
            const uint32_t dst = base + sl * 16384 + w * 8192, ab = bars + B_A + (w * 8 + sl) * 8;
            const uint32_t cell = base + OFF_ONES + (lane & 7) * 128 + ((((lane & 7) >> 1) ^ 2) << 5);
            #pragma unroll 1
            for (int x = 0; x < 2; x++) {
                bool pend = lane < 6 && !(x && sl == 2);
                const unsigned* fl = &Q.s->row[src_cta][256 + (x * 2 + w) * 8];
                const uint32_t gate = x ? bars + B_F2 + w * 8 : w ? bars + B_F1 : bars + B_F0;
                const uint4* src = &Q.s->xch[x][src_cta][w * 512];
                const uint32_t hold = x && lane >= 2 ? 3u : 0u;
                const bool paced = x && lane >= 4;
                const uint32_t pace = lane < 4 ? bars + B_A + (w * 8 + 3) * 8 : ab - 16;
                uint32_t seen = 0, pm = 63;
                int it = 0;
                mbar_wait(bars + B_GO, x);
                #pragma unroll 1
                do {
                    if (pend && !seen) { poll_async(cell + x * 16, fl); seen = lds1(cell + x * 16) | (++it > 8 * SPIN_LIMIT); }
                    if (pend && seen && !(pm & hold) && mbar_test(gate, 0) && (!paced || mbar_test(pace, 0))) { bulk_load_mc(dst, src, 8192, ab); pend = false; }
                    pm = __ballot_sync(~0u, pend);
                } while (pm);
            }
        } else {
            const int w = warp - 9;
            #pragma unroll 1
            for (int x = 0; x < 2; x++) {
                const uint32_t so = x * 16384 + w * 8192;
                mbar_wait(x ? bars + B_FP + w * 8 : w ? bars + B_FQ : bars + B_F0, 0);
                bar_sync(3 + w, 160);
                if (elect_one()) {
                    bulk_store(&Q.s->xch[x][cta][w * 512], base + so, 8192);
                    bulk_commit();
                    bulk_push(rbase + (so ^ 16384), base + so, 8192, rbars + B_A + (w * 8 + (x ^ 1)) * 8);
                    if (x) {
                        #pragma unroll
                        for (int u = 3; u < 8; u++) mbar_expect_tx(bars + B_A + (w * 8 + u) * 8, 8192);
                    }
                    const uint32_t fo = x ? B_F2 + w * 8 : B_F1;
                    mbar_arrive(bars + fo); mbar_arrive_cl(rbars + fo);
                    if (w == 0) mbar_arrive(bars + B_GO);
                    bulk_wait0();
                    st_rlx(&Q.s->row[cta][256 + (x * 2 + w) * 8], 1);
                    if (x == 0) mbar_arrive_cl(rbars + B_FP + w * 8);
                }
                __syncwarp();
                if (x) {
                    #pragma unroll 1
                    for (int r = 0; r < 2; r++) {
                        float a = 0.f, b = 0.f;
                        #pragma unroll 2
                        for (int c = 0; c < 8; c++) {
                            uint32_t u[4];
                            lds4(u, base + so + (r * 32 + lane) * 128 + ((c ^ (lane & 7)) << 4));
                            #pragma unroll
                            for (int k = 0; k < 4; k++) { a = fmaf(bf_lo(u[k]), bf_lo(u[k]), a); b = fmaf(bf_hi(u[k]), bf_hi(u[k]), b); }
                        }
                        st_rlx(&Q.s->row[cta][128 + w * 64 + r * 32 + lane], __float_as_uint(a + b) | 1u);
                    }
                }
                const unsigned* rp = &Q.s->row[i * 8][x * 128 + w * 64 + lane * 2];
                uint32_t v[16], ok;
                int it = 0;
                #pragma unroll 1
                do {
                    ok = 1;
                    #pragma unroll
                    for (int u = 0; u < 8; u++) asm volatile("ld.relaxed.gpu.global.v2.b32 {%0,%1}, [%2];" : "=r"(v[2 * u]), "=r"(v[2 * u + 1]) : "l"(rp + u * 288) : "memory");
                    #pragma unroll
                    for (int u = 0; u < 8; u++) asm("lop3.b32 %0, %0, %1, %2, 0x80;" : "+r"(ok) : "r"(v[2 * u]), "r"(v[2 * u + 1]));
                } while (__any_sync(~0u, !ok) && ++it < SPIN_LIMIT);
                float a = 0.f, b = 0.f;
                #pragma unroll
                for (int u = 0; u < 8; u++) { a += __uint_as_float(v[2 * u]); b += __uint_as_float(v[2 * u + 1]); }
                if (x) { a = rcp(fmaf(a, 1.f / 512.f, 1e-5f)); b = rcp(fmaf(b, 1.f / 512.f, 1e-5f)); }
                const uint32_t ta = base + OFF_ONES + (w * 4 + (lane >> 3)) * 256 + (((lane >> 3) ^ 1) << 5) + ((lane >> 2) & 1) * 128 + (lane & 3) * 8;
                sts1(ta, __float_as_uint(a)); sts1(ta + 4, __float_as_uint(b));
                __syncwarp();
                if (lane == 0) mbar_arrive(bars + B_TB + w * 8);
            }
        }
        poll_drain();
    } else {
        asm volatile("setmaxnreg.inc.sync.aligned.u32 232;");
        const int w = warp >> 2, g = lane >> 2, q = lane & 3;
        const bool elect = (tid & 127) == 0;
        const uint32_t lm0 = base + (warp * 16 + ((lane >> 3) & 1) * 8 + (lane & 7)) * 128 + (((lane >> 4) ^ (lane & 7)) << 4);
        const uint32_t ro0 = base + (warp * 16 + g) * 128 + (((2 * q) ^ g) << 4);
        const uint32_t dbase = mkdesc(base, 16), dring = dbase + (OFF_RING >> 4);
        float mean0, mean1, sp0, sp1;
        uint32_t anc = lane;
        uint32_t ea[32];
        if (w == 1) bar_arrive(6, 256);
        {
            uint32_t xa[128];
            DualExp de;
            auto centre = [&](int u0, int u1) {
                const uint32_t m0 = pack2(mean0, mean0), m1 = pack2(mean1, mean1);
                #pragma unroll
                for (int u = u0; u < u1; u++) { xa[2 * u] = sub2(xa[2 * u], m0); xa[2 * u + 1] = sub2(xa[2 * u + 1], m1); }
            };
            const uint32_t sso = OFF_ONES + warp * 256 + (((warp & 3) ^ 1) << 5) + (g >> 2) * 128 + (g & 3) * 8;
            {
                float rs[4][4] = {}, sq[4][4] = {};
                auto stats = [&](const uint32_t* xc) {
                    #pragma unroll
                    for (int ks = 0; ks < 4; ks++) {
                        const uint32_t* a = xc + ks * 4;
                        mma16816(rs[ks], a, 0x3f803f80u, 0x3f803f80u);
                        const uint32_t b0 = e ? a[2] : a[0], b1 = e ? a[3] : a[1];
                        mma1688(sq[(ks & 1) * 2], b0, b1, b0); mma1688(sq[(ks & 1) * 2 + 1], b0, b1, b1);
                    }
                };
                #pragma unroll
                for (int c = 0; c < 8; c++) {
                    mbar_wait(bars + B_A + c * 8, 0);
                    #pragma unroll
                    for (int ks = 0; ks < 4; ks++) ldsm4(xa + c * 16 + ks * 4, (c ^ j) * 16384 + (lm0 ^ (ks << 5)));
                    stats(xa + c * 16);
                }
                const float ss0 = (g & 1) ? sq[0][1] + sq[2][1] : sq[0][0] + sq[2][0], ss1 = (g & 1) ? sq[1][3] + sq[3][3] : sq[1][2] + sq[3][2];
                asm volatile("{\n.reg .pred p;\nsetp.eq.u32 p, %4, %5;\n@p st.async.weak.shared::cluster.mbarrier::complete_tx::bytes.v2.f32 [%0], {%1,%2}, [%3];\n}"
                             :: "r"(rbase + sso), "f"(ss0), "f"(ss1), "r"(rbars + B_SS), "r"(q), "r"(g >> 1) : "memory");
                de.c0 = __shfl_sync(~0u, ss0, g * 4 + (g >> 1)); de.c1 = __shfl_sync(~0u, ss1, g * 4 + (g >> 1));
                if (lane == 0) mbar_arrive(bars + B_XC);
                mean0 = ((rs[0][0] + rs[1][0]) + (rs[2][0] + rs[3][0])) * (1.f / 512.f);
                mean1 = ((rs[0][2] + rs[1][2]) + (rs[2][2] + rs[3][2])) * (1.f / 512.f);
                de.c0 = fmaf(de.c0, 1.f / 512.f, -mean0 * mean0); de.c1 = fmaf(de.c1, 1.f / 512.f, -mean1 * mean1);
                centre(0, 40);
            }
            auto stage = [&](float* acc, auto M, auto SL, uint32_t db, uint32_t fb, uint32_t ph, bool signal) {
                constexpr int m = decltype(M)::v, sl = decltype(SL)::v;
                mbar_wait(fb + sl * 8, ph);
                wg_fence();
                static_for<8>([&](auto K) { constexpr int ks = decltype(K)::v; wgmma_rs_n64<sl * 1024 + ks * 128>(acc, xa + (m * 8 + ks) * 4, db, m + ks); });
                wg_commit();
                if (signal) bar_arrive(7 - w, 256);
                if (m > 0) { wg_wait<1>(); if (elect) mbar_arrive(fb + (B_EMPTY - B_FULL) + ((sl + 5) % 6) * 8); }
            };
            auto phi_store = [&]() {
                const float ip0 = rcp(de.sp0), ip1 = rcp(de.sp1), im0 = rcp(de.sm0), im1 = rcp(de.sm1);
                const uint32_t f[4] = {pack2(ip0, ip0), pack2(ip1, ip1), pack2(im0, im0), pack2(im1, im1)};
                #pragma unroll
                for (int u = 0; u < 4; u++) {
                    const uint32_t a = 32768 + (u & 1) * 1024 + (u >> 1) * 16384;
                    sts4(a + ro0, mul2(ea[u], f[u]), mul2(ea[4 + u], f[u]), mul2(ea[8 + u], f[u]), mul2(ea[12 + u], f[u]));
                    sts4(a + (ro0 ^ 16), mul2(ea[16 + u], f[u]), mul2(ea[20 + u], f[u]), mul2(ea[24 + u], f[u]), mul2(ea[28 + u], f[u]));
                }
            };
            #pragma unroll 1
            for (int it = 0; ; it = 2) {
                float tt[32];
                {
                    float acc[32], pp[32];
                    const uint32_t db = dring + it * 1024, fb = bars + B_FULL + it * 8;
                    bar_sync(6 + w, 256);
                    static_for<4>([&](auto M) {
                        constexpr int m = decltype(M)::v;
                        stage(acc, M, M, db, fb, it >> 1, m == 3);
                        if (m == 1 && it - w == 2) bar_sync(8, 256);
                        if (m < 3 && it == 0) centre(40 + 8 * m, 48 + 8 * m);
                    });
                    if (it == 0) {
                        mbar_wait(bars + B_SS, 0);
                        de.c0 = rsq(fmaxf(fmaf(__uint_as_float(lds1(base + sso)), 1.f / 512.f, de.c0), 0.f) + 1e-5f) * 1.4426950408889634f;
                        de.c1 = rsq(fmaxf(fmaf(__uint_as_float(lds1(base + sso + 4)), 1.f / 512.f, de.c1), 0.f) + 1e-5f) * 1.4426950408889634f;
                        mbar_wait(bars + B_BD, 0);
                    }
                    wg_wait<0>();
                    if (elect) mbar_arrive(fb + (B_EMPTY - B_FULL) + 24);
                    reg_fence<32>(acc);
                    uint32_t kp[16];
                    #pragma unroll
                    for (int u = 0; u < 16; u++) kp[u] = pack2(acc[2 * u], acc[2 * u + 1]);
                    wg_fence();
                    static_for<4>([&](auto K) { constexpr int ks = decltype(K)::v; wgmma_rs_n64<(oBD >> 4) + ks * 128>(pp, kp + ks * 4, dbase, ks); });
                    wg_commit();
                    wg_wait<0>();
                    reg_fence<32>(pp);
                    if (it && elect) mbar_arrive_cl(rbars + B_FQ);
                    de.init(pp, tt);
                    reg_fence<32>(tt);
                }
                #pragma unroll
                for (int t = 0; t < 2; t++) de.unit(tt + 4 * t, ea + 4 * t);
                keep_live<8>(ea);
                if (it) {
                    #pragma unroll
                    for (int t = 2; t < 8; t++) de.unit(tt + 4 * t, ea + 4 * t);
                    break;
                }
                float va[32];
                bar_sync(6 + w, 256);
                static_for<3>([&](auto M) {
                    constexpr int m = decltype(M)::v, t0 = 2 + 2 * m, t1 = t0 + 2;
                    stage(va, M, IC<(m + 4) % 6>{}, dring + 65536, bars + B_FULL, m >> 1, m == 2 && w == 0);
                    anchor(anc);
                    reg_fence<4 * (t1 - t0)>(tt + 4 * t0);
                    #pragma unroll
                    for (int t = t0; t < t1; t++) de.unit(tt + 4 * t, ea + 4 * t);
                    keep_live<4 * (t1 - t0)>(ea + 4 * t0);
                });
                stage(va, IC<3>{}, IC<1>{}, dring + 65536, bars + B_FULL, 1, w == 1);
                anchor(anc); keep_live<32>(ea); reg_fence<1>(&de.sp0); reg_fence<1>(&de.sp1); reg_fence<1>(&de.sm0); reg_fence<1>(&de.sm1);
                phi_store();
                wg_wait<0>();
                if (elect) mbar_arrive(bars + B_EMPTY + 8);
                reg_fence<32>(va);
                {
                    const float r0 = de.c0 * 0.6931471805599453f, r1 = de.c1 * 0.6931471805599453f;
                    #pragma unroll
                    for (int ks = 0; ks < 4; ks++) {
                        const float* v = va + ks * 8;
                        stsm4(65536 + (lm0 ^ (ks << 5)), pack2(v[0] * r0, v[1] * r0), pack2(v[2] * r1, v[3] * r1), pack2(v[4] * r0, v[5] * r0), pack2(v[6] * r1, v[7] * r1));
                    }
                    fence_async_smem();
                    if (w == 0) {
                        bar_arrive(1, 256);
                    } else {
                        bar_sync(1, 256);
                        float kv0[36], kv1[36];
                        constexpr int OB = (65536 >> 4) + ((((OFF_ONES - 65536) >> 4) - 1) << 16);
                        wg_fence();
                        static_for<8>([&](auto K) { constexpr int ks = decltype(K)::v; wgmma_st_n72<2048 + ks * 128, OB + ks * 128 - ((ks * 128) << 16)>(kv0, dbase, dbase, ks); });
                        wg_commit();
                        mbar_wait(bars + B_ZR, 0);
                        float4* dst = &Q.s->kv[j][tid - 128];
                        const float rm4 = (warp - 4) * 4 + (g >> 1) == i ? __uint_as_float(lds1(base + OFF_RM4 + ((g & 1) * 2 + (q & 1)) * 4)) : 0.f;
                        wg_fence();
                        static_for<8>([&](auto K) { constexpr int ks = decltype(K)::v; wgmma_st_n72<3072 + ks * 128, OB + ks * 128 - ((ks * 128) << 16)>(kv1, dbase, dbase, ks); });
                        wg_commit();
                        bar_arrive(8, 256);
                        auto reds = [&](const float* kv, float z, float4* d4) {
                            float u[8];
                            #pragma unroll
                            for (int t = 0; t < 8; t++) u[t] = (warp & 2) ? ((warp & 1) ? kv[24 + t] : kv[16 + t]) : ((warp & 1) ? kv[8 + t] : kv[t]);
                            red_f4(d4, u[0], u[1], u[2]); red_f4(d4 + 128, u[3], u[4], u[5]); red_f4(d4 + 256, u[6], u[7], z);
                        };
                        wg_wait<1>();
                        reg_fence<36>(kv0);
                        reds(kv0, q >= 2 ? rm4 : q ? kv0[34] : kv0[32], dst);
                        wg_wait<0>();
                        reg_fence<36>(kv1);
                        reds(kv1, (q & 1) ? kv1[34] : kv1[32], dst + 384);
                        bar_arrive(2, 256);
                        if (elect) { mbar_arrive(bars + B_F0); mbar_arrive_cl(rbars + B_F0); }
                    }
                }
            }
            sp0 = de.sp0; sp1 = de.sp1;
            const float r0 = sp0 * rcp(de.sm0), r1 = sp1 * rcp(de.sm1);
            const uint32_t b0 = pack2(r0, r0), b1 = pack2(r1, r1);
            #pragma unroll
            for (int t = 0; t < 8; t++) { ea[4 * t + 2] = mul2(ea[4 * t + 2], b0); ea[4 * t + 3] = mul2(ea[4 * t + 3], b1); }
        }
        unsigned* rowp = &Q.s->row[cta][warp * 16 + g];
        uint32_t xr[16], tag, lt0;
        {
            float na[36];
            mbar_wait(bars + B_KVB, 0);
            wg_fence();
            static_for<8>([&](auto K) { constexpr int ks = decltype(K)::v; wgmma_rs_n72<(oKV >> 4) + (ks >> 2) * 1024 + (ks & 3) * 128 + ((ks < 4 ? 2047 : 1024) << 16)>(na, ea + ks * 4, dbase, ks); });
            wg_commit();
            lt0 = base + ((lane >> 4) * 8 + (lane & 7)) * 128 + ((((warp & 3) * 2 + ((lane >> 3) & 1)) ^ (lane & 7)) << 4);
            #pragma unroll
            for (int ks = 0; ks < 4; ks++) ldsm4t(xr + ks * 4, lt0 + w * 8192 + ks * 2048);
            bar_sync(11 + w, 128);
            tag = lds1(base + OFF_RM4 + 16);
            uint32_t kk[5] = {(g & 3) == 0, (g & 3) == 1, (g & 3) == 2, (g & 3) == 3, ro0};
            keep_live<5>(kk);
            wg_wait<0>();
            reg_fence<36>(na);
            const float i0 = rcp(fmaf(sp0, 1e-6f, na[32])), i1 = rcp(fmaf(sp1, 1e-6f, na[34]));
            #pragma unroll
            for (int t = 0; t < 8; t++) { na[4 * t] *= i0; na[4 * t + 1] *= i0; na[4 * t + 2] *= i1; na[4 * t + 3] *= i1; }
            #pragma unroll
            for (int u = 0; u < 4; u++) {
                const float* v = na + (u & 1) * 16 + (u >> 1) * 2;
                sts4((u >> 1) * 1024 + (kk[4] ^ ((u & 1) * 16)), pack2(v[0], v[1]) | kk[0], pack2(v[4], v[5]) | kk[1], pack2(v[8], v[9]) | kk[2], pack2(v[12], v[13]) | kk[3]);
            }
            fence_async_smem();
            bar_sync(3 + w, 160);
            float t0 = mean0 * (1.f / 32.f), t1 = mean1 * (1.f / 32.f);
            #pragma unroll
            for (int u = 0; u < 4; u++) {
                uint32_t m[4]; lds4(m, base + OFF_RM + q * 64 + u * 16);
                t0 = fmaf(na[8 * u], __uint_as_float(m[0]), t0); t0 = fmaf(na[8 * u + 1], __uint_as_float(m[1]), t0);
                t0 = fmaf(na[8 * u + 4], __uint_as_float(m[2]), t0); t0 = fmaf(na[8 * u + 5], __uint_as_float(m[3]), t0);
                t1 = fmaf(na[8 * u + 2], __uint_as_float(m[0]), t1); t1 = fmaf(na[8 * u + 3], __uint_as_float(m[1]), t1);
                t1 = fmaf(na[8 * u + 6], __uint_as_float(m[2]), t1); t1 = fmaf(na[8 * u + 7], __uint_as_float(m[3]), t1);
            }
            row_store(rowp, t0, t1, q);
        }
        const uint32_t dA = dbase + w * 512, abar = bars + B_A + w * 64;
        const uint32_t tga = pin(base + warp * 2048 + g * 128 + q * 32 + (g & 3) * 4 + (lane & 16));
        const uint32_t tb0 = base + OFF_ONES + w * 1024;
        uint32_t hr[16];
        {
            float h0[32], hb[32];
            uint32_t wa[128], tm[16];
            mbar_wait(bars + B_FULL, 0);
            #pragma unroll
            for (int u = 0; u < 8; u++) ldsm4t(wa + u * 4, lt0 + OFF_RING + (((u >> 2) ^ e) * 4 + (u & 3)) * 2048);
            #pragma unroll
            for (int u = 0; u < 16; u++) { h0[2 * u] = bf_lo(xr[u]); h0[2 * u + 1] = bf_hi(xr[u]); }
            wg_fence();
            static_for<4>([&](auto K) { constexpr int ks = decltype(K)::v; wgmma_rk_n64<ks * 2>(h0, wa + ks * 4, dA, 1); });
            mbar_wait(bars + B_FULL + 8, 0); mbar_wait(bars + B_FULL + 16, 0); mbar_wait(bars + B_FULL + 24, 0);
            #pragma unroll
            for (int u = 8; u < 32; u++) ldsm4t(wa + u * 4, lt0 + OFF_RING + u * 2048);
            mbar_wait(abar + 8, 1);
            wg_fence();
            static_for<4>([&](auto K) { constexpr int ks = decltype(K)::v; wgmma_rk_n64<1024 + ks * 2>(h0, wa + 16 + ks * 4, dA, 1); });
            wg_commit();
            const uint32_t kt = pin((uint32_t)(g == 4 * (q & 1)) | ((uint32_t)(g == 2 + 4 * (q & 1)) << 16)), lth = pin(lt0 + 16384 + w * 8192);
            wg_wait<0>();
            reg_fence<32>(h0);
            bar_sync(11 + w, 128);
            if (elect) mbar_arrive_cl(rbars + B_FP + w * 8);
            #pragma unroll 1
            for (int attempt = 0; ; attempt++) {
                if (attempt) {
                    #pragma unroll 1
                    for (int n = 2; n < 8; n++) settle(base + n * 16384 + warp * 2048 + lane * 16, &Q.s->xch[0][(cta & ~1) ^ n][warp * 128 + lane], tga + n * 16384);
                    bar_sync(11 + w, 128);
                }
                #pragma unroll
                for (int u = 0; u < 32; u++) hb[u] = h0[u];
                reg_fence<32>(hb);
                anchor(anc);
                uint32_t tg[4] = {}, ok = 1;
                static_for<6>([&](auto N) {
                    constexpr int n = 2 + decltype(N)::v;
                    mbar_wait(abar + n * 8, 1);
                    wg_fence();
                    static_for<4>([&](auto K) { constexpr int ks = decltype(K)::v; wgmma_rk_n64<n * 1024 + ks * 2>(hb, wa + n * 16 + ks * 4, dA, 1); });
                    wg_commit();
                    if (n > 2) { asm("lop3.b32 %0, %0, %1, %2, 0x80;" : "+r"(ok) : "r"(tg[0]), "r"(tg[1])); asm("lop3.b32 %0, %0, %1, %2, 0x80;" : "+r"(ok) : "r"(tg[2]), "r"(tg[3])); }
                    tags_load(tg, tga + n * 16384);
                    if (n == 7) {
                        mbar_wait(bars + B_TB + w * 8, 0);
                        #pragma unroll
                        for (int t = 0; t < 8; t++) asm volatile("ld.shared.v2.b32 {%0,%1}, [%2];" : "=r"(tm[2 * t]), "=r"(tm[2 * t + 1]) : "r"(tb0 + q * 8 + t * 128 + (((t >> 1) ^ 1) << 5)) : "memory");
                    }
                    if (n == 2 && elect && !attempt) mbar_arrive(bars + B_EMPTY);
                    if (n == 5 && lane == 0 && (warp & 3) && !attempt) mbar_arrive(bars + B_EMPTY + (warp & 3) * 8);
                });
                asm("lop3.b32 %0, %0, %1, %2, 0x80;" : "+r"(ok) : "r"(tg[0]), "r"(tg[1])); asm("lop3.b32 %0, %0, %1, %2, 0x80;" : "+r"(ok) : "r"(tg[2]), "r"(tg[3]));
                const bool good = bar_and(11 + w, 128, ok);
                wg_wait<0>();
                reg_fence<32>(hb);
                if (good || attempt) break;
            }
            #pragma unroll
            for (int ks = 0; ks < 4; ks++) {
                uint32_t o[4];
                #pragma unroll
                for (int u = 0; u < 4; u++)
                    o[u] = pack2(hb[8 * ks + 2 * u] - __uint_as_float(tm[4 * ks + (u & 2)]), hb[8 * ks + 2 * u + 1] - __uint_as_float(tm[4 * ks + (u & 2) + 1])) | kt;
                stsm4t(lth + ks * 2048, o[0], o[1], o[2], o[3]);
            }
            fence_async_smem();
            bar_sync(3 + w, 160);
            anchor(anc); reg_fence<32>(hb);
            #pragma unroll
            for (int u = 0; u < 16; u++) hr[u] = pack2(hb[2 * u], hb[2 * u + 1]);
            keep_live<16>(hr);
        }
        uint32_t act[56];
        uint32_t slot = 4, ph = 0;
        #pragma unroll 1
        for (int pass = 0; pass < 2; pass++) {
            float acc[112];
            uint32_t prev = 0;
            #pragma unroll 1
            for (int n = 0; n < 8; n++) {
                const int c = n ^ (n < 2 ? 1 : 0);
                const uint32_t da = dA + c * 1024;
                if (pass == 0 && n > 0) {
                    const int nn = n < 2 ? 2 : n;
                    const uint32_t dst = base + nn * 16384 + warp * 2048 + lane * 16;
                    const uint4* src = &Q.s->xch[1][(cta & ~1) ^ nn][warp * 128 + lane];
                    if (n == 2) settle(dst, src, tga + 32768);
                    else {
                        mbar_wait(abar + c * 8, n == 1 ? 1 : 0);
                        if (n == 1) fetch(dst, src);
                        else {
                            uint32_t t[4];
                            tags_load(t, tga + c * 16384);
                            if (__any_sync(~0u, stale(t[0], t[1], t[2], t[3], 1u))) settle(dst, src, tga + c * 16384);
                        }
                    }
                }
                const uint32_t db = dring + (255 << 16) + slot * 1024;
                mbar_wait(bars + B_FULL + slot * 8, ph);
                wg_fence();
                wgmma_ss_n224<0, 0>(acc, da, db, n);
                wgmma_ss_n224<2, 128>(acc, da, db, 1);
                wg_commit();
                wg_wait<1>();
                if (elect && n > 0) mbar_arrive(bars + B_EMPTY + prev * 8);
                mbar_wait(bars + B_FULL + slot * 8 + 8, ph);
                wg_fence();
                wgmma_ss_n224<4, 1024>(acc, da, db, 1);
                wgmma_ss_n224<6, 1152>(acc, da, db, 1);
                wg_commit();
                wg_wait<1>();
                if (elect) mbar_arrive(bars + B_EMPTY + slot * 8);
                prev = slot + 1; slot += 2; if (slot == 6) { slot = 0; ph ^= 1; }
            }
            wg_wait<0>();
            if (elect) mbar_arrive(bars + B_EMPTY + prev * 8);
            reg_fence<112>(acc);
            if (pass == 0) {
                #pragma unroll
                for (int u = 0; u < 56; u++) act[u] = pack2_relu(acc[2 * u], acc[2 * u + 1]);
            } else {
                if (elect) mbar_arrive_cl(rbars + B_F3 + w * 8);
                #pragma unroll
                for (int u = 0; u < 56; u++) act[u] = mul2(act[u], pack2(acc[2 * u], acc[2 * u + 1]));
            }
        }
        float dd[2][32], r0, r1;
        uint32_t rx[16], ry[16], rz[16], rw[16];
        const uint32_t ib = warp * 2048 + lane * 16;
        uint32_t mo, lm1;
        const char* mb;
        char* gas[3] = {};
        auto rx_load = [&](uint32_t* r, int plane) {
            #pragma unroll
            for (int b = 0; b < 4; b++) ld_rlx128(r + b * 4, mb + plane * 2097152 + b * 128);
        };
        auto pp_load = [&](int m) {
            mbar_wait(bars + B_PP + w * 32 + m * 8, 0);
            #pragma unroll
            for (int b = 0; b < 4; b++) lds4(ry + b * 4, base + ib + ((m + 6) & 7) * 16384 + b * 512);
        };
        auto send = [&](auto S) {
            constexpr int s = decltype(S)::v, m = s >> 1;
            float* d = dd[s & 1];
            reg_fence<32>(d);
            if (s < 3 && elect) mbar_arrive(bars + B_EMPTY + s * 16);
            uint32_t pk[16];
            if constexpr (s & 1) {
                pp_load(m);
                char* ga = gas[m] + (m == 2 ? 0 : 3 - m) * 2097152;
                #pragma unroll
                for (int u = 0; u < 16; u++) pk[u] = add2(pack2(d[2 * u], d[2 * u + 1]), ry[u]);
                #pragma unroll
                for (int b = 0; b < 4; b++) {
                    pk[5 * b] = (pk[5 * b] & ~1u) | (m == 2 ? 0u : tag);
                    st_rlx128(ga + b * 128, pk[4 * b], pk[4 * b + 1], pk[4 * b + 2], pk[4 * b + 3]);
                }
            } else {
                if (s == 0) mbar_wait(bars + B_F3 + w * 8, 0);
                #pragma unroll
                for (int u = 0; u < 16; u++) pk[u] = pack2(d[2 * u], d[2 * u + 1]);
                #pragma unroll
                for (int b = 0; b < 4; b++)
                    asm volatile("st.async.weak.shared::cluster.mbarrier::complete_tx::bytes.v4.b32 [%0], {%1,%2,%3,%4}, [%5];"
                                 :: "r"(rbase + ib + ((m + 6) & 7) * 16384 + b * 512), "r"(pk[4 * b]), "r"(pk[4 * b + 1]), "r"(pk[4 * b + 2]), "r"(pk[4 * b + 3]), "r"(rbars + B_PP + w * 32 + m * 8) : "memory");
            }
        };
        static_for<8>([&](auto S) {
            constexpr int s = decltype(S)::v, b5 = s % 5;
            bar_sync(6 + w, 256);
            mbar_wait(bars + (b5 < 3 ? B_FULL + b5 * 16 : B_FX - 24 + b5 * 8), s >= 5);
            wg_fence();
            static_for<14>([&](auto K) { constexpr int ks = decltype(K)::v; wgmma_rs_n64<ks * 128>(dd[s & 1], act + ks * 4, dbase + (b5 < 3 ? b5 + 4 : b5 - 2) * 2048 + ((s + 1) << 16), ks); });
            wg_commit();
            if (s < 7 || w == 0) bar_arrive(7 - w, 256);
            if constexpr (s == 0) {
                const uint32_t lt1 = base + w * 8192 + ((lane >> 4) * 8 + (lane & 7)) * 128 + ((((warp & 3) * 2 + ((lane >> 3) & 1)) ^ (lane & 7)) << 4);
                #pragma unroll
                for (int ks = 0; ks < 4; ks++) stsm4t(lt1 + ks * 2048, hr[4 * ks], hr[4 * ks + 1], hr[4 * ks + 2], hr[4 * ks + 3]);
                mbar_wait(bars + B_TB + w * 8, 1);
                const uint32_t tba = tb0 + (warp & 3) * 256 + (((warp & 3) ^ 1) << 5) + g * 4;
                r0 = __uint_as_float(lds1(tba)); r1 = __uint_as_float(lds1(tba + 128));
                lm1 = pin(base + 32768 + (warp * 16 + ((lane >> 3) & 1) * 8 + (lane & 7)) * 128 + (((lane >> 4) ^ (lane & 7)) << 4));
                const uint64_t a = (uint64_t)&Q.s->xch[0][cta][warp * 128 + (lane >> 3) * 32 + (lane & 7)];
                mo = (uint32_t)a;
                mb = (const char*)(((uint64_t)pin((uint32_t)(a >> 32)) << 32) | pin(mo));
                #pragma unroll
                for (int u = 0; u < 3; u++) gas[u] = (char*)(((uint64_t)pin((uint32_t)(a >> 32)) << 32) | pin(mo ^ ((3 - u) << 15)));
            } else {
                if (s == 5) rx_load(rx, 3);
                if (s == 7) { rx_load(rw, 0); anchor(anc); }
                wg_wait<1>();
                send(IC<s - 1>{});
                if (s == 1) {
                    #pragma unroll
                    for (int ks = 0; ks < 4; ks++) ldsm4(hr + ks * 4, (lm1 - 32768) ^ (ks << 5));
                }
                if (s == 6) { anchor(anc); rx_load(rz, 2); }
            }
            anchor(anc);
        });
        {
            float hb[32];
            const float* d = dd[1];
            #pragma unroll
            for (int u = 0; u < 16; u++) { hb[2 * u] = bf_lo(hr[u]); hb[2 * u + 1] = bf_hi(hr[u]); }
            reg_fence<32>(hb);
            anchor(anc);
            wg_wait<0>();
            reg_fence<32>(dd[1]);
            #pragma unroll
            for (int u = 0; u < 32; u++) hb[u] = fmaf(d[u], (u & 2) ? r1 : r0, hb[u]);
            reg_fence<32>(hb);
            anchor(anc); keep_live<16>(rz); keep_live<16>(rx);
            int it = 0;
            #pragma unroll 1
            while (__builtin_expect(!!__any_sync(~0u, stale(rx[0], rx[5], rx[10], rx[15], tag) | stale(rz[0], rz[5], rz[10], rz[15], tag)), 0) && ++it < SPIN_LIMIT) { rx_load(rx, 3); rx_load(rz, 2); }
            #pragma unroll
            for (int b = 0; b < 4; b++) { rx[5 * b] |= 1u; rz[5 * b] &= ~1u; }
            #pragma unroll
            for (int u = 0; u < 16; u++) rx[u] = add2(rx[u], rz[u]);
            keep_live<16>(rx);
            anchor(anc); keep_live<16>(rw);
            #pragma unroll 1
            while (__builtin_expect(!!__any_sync(~0u, stale(rw[0], rw[5], rw[10], rw[15], 0u)), 0) && ++it < SPIN_LIMIT) rx_load(rw, 0);
            {
                #pragma unroll
                for (int u = 0; u < 16; u++) rx[u] = add2(rx[u], rw[u]);
                keep_live<16>(rx);
                pp_load(3);
            }
            #pragma unroll
            for (int ks = 0; ks < 4; ks++) {
                uint32_t o[4];
                #pragma unroll
                for (int u = 0; u < 4; u++) {
                    const uint32_t t = add2(rx[4 * ks + u], ry[4 * ks + u]);
                    const float r = (u & 1) ? r1 : r0;
                    o[u] = pack2(fmaf(bf_lo(t), r, hb[8 * ks + 2 * u]), fmaf(bf_hi(t), r, hb[8 * ks + 2 * u + 1]));
                }
                stsm4(lm1 ^ (ks << 5), o[0], o[1], o[2], o[3]);
            }
            if (tag > 1) sts1(base, anc);
            fence_async_smem();
            __syncwarp();
            if (elect_one()) {
                tma2d_store(&P.tout, base + 32768 + warp * 2048, 64 * j, i * 128 + warp * 16);
                bulk_commit();
                bulk_wait0_read();
            }
        }
    }
}

typedef CUresult (*EncodeFn)(CUtensorMap*, CUtensorMapDataType, cuuint32_t, void*, const cuuint64_t*, const cuuint64_t*, const cuuint32_t*,
                             const cuuint32_t*, CUtensorMapInterleave, CUtensorMapSwizzle, CUtensorMapL2promotion, CUtensorMapFloatOOBfill);

void make_map(EncodeFn enc, CUtensorMap* m, const void* ptr, int nd, const cuuint64_t* dims, const cuuint64_t* strides, const cuuint32_t* box) {
    const cuuint32_t es[3] = {1, 1, 1};
    enc(m, CU_TENSOR_MAP_DATA_TYPE_BFLOAT16, nd, const_cast<void*>(ptr), dims, strides, box, es, CU_TENSOR_MAP_INTERLEAVE_NONE,
        CU_TENSOR_MAP_SWIZZLE_128B, CU_TENSOR_MAP_L2_PROMOTION_L2_128B, CU_TENSOR_MAP_FLOAT_OOB_FILL_NONE);
}
void make_2d(EncodeFn enc, CUtensorMap* m, const void* ptr, cuuint64_t cols, cuuint64_t rows, cuuint32_t bc, cuuint32_t br) {
    const cuuint64_t dims[2] = {cols, rows}, strides[1] = {cols * 2};
    const cuuint32_t box[2] = {bc, br};
    make_map(enc, m, ptr, 2, dims, strides, box);
}

}

extern "C" void kernel_launch(void* const* d_in, const int* in_sizes, int n_in, void* d_out, int out_size) {
    (void)in_sizes; (void)n_in; (void)out_size;
    static EncodeFn enc = nullptr;
    static void* scratch = nullptr;
    if (!enc) {
        void* fn = nullptr; cudaDriverEntryPointQueryResult qr;
        cudaGetDriverEntryPoint("cuTensorMapEncodeTiled", &fn, cudaEnableDefault, &qr);
        enc = (EncodeFn)fn;
        cudaGetSymbolAddress(&scratch, g_scratch);
        cudaFuncSetAttribute(fused_kernel, cudaFuncAttributeMaxDynamicSharedMemorySize, SMEM_TOTAL);
    }
    Params P; Ptrs Q;
    Q.x = (const __nv_bfloat16*)d_in[0]; Q.wqkv = (const __nv_bfloat16*)d_in[1]; Q.wphi = (const __nv_bfloat16*)d_in[2]; Q.wo = (const __nv_bfloat16*)d_in[3];
    Q.s = (Scratch*)(((uintptr_t)scratch + 131071) & ~(uintptr_t)131071);
    P.wf[0] = (const __nv_bfloat16*)d_in[5]; P.wf[1] = (const __nv_bfloat16*)d_in[6]; P.wf[2] = (const __nv_bfloat16*)d_in[7];
    make_2d(enc, &P.tx, d_in[0], 512, 2048, 64, 128);
    make_2d(enc, &P.tqkv, Q.wqkv, 1536, 512, 64, 128);
    make_2d(enc, &P.two, Q.wo, 512, 512, 64, 128);
    const cuuint64_t d3[3] = {64, 512, 28}, s3[2] = {3584, 128};
    const cuuint32_t b3[3] = {64, 32, 3};
    make_map(enc, &P.tg3, P.wf[0], 3, d3, s3, b3);
    make_map(enc, &P.tu3, P.wf[1], 3, d3, s3, b3);
    make_2d(enc, &P.tgh, P.wf[0], 1792, 512, 32, 32);
    make_2d(enc, &P.tuh, P.wf[1], 1792, 512, 32, 32);
    make_2d(enc, &P.td192, P.wf[2], 512, 1792, 64, 192);
    make_2d(enc, &P.td32, P.wf[2], 512, 1792, 64, 32);
    make_2d(enc, &P.tout, d_out, 512, 2048, 64, 16);
    fused_kernel<<<128, 384, SMEM_TOTAL, cudaStreamPerThread>>>(Q, P);
}
```
